```python
import torch

def _softmax(x, axis=-1):
    return torch.softmax(x, dim=axis)

def _gelu(x):
    return torch.nn.functional.gelu(x, approximate='tanh')

def _silu(x):
    return torch.nn.functional.silu(x)

def _sigmoid(x):
    return torch.sigmoid(x)

def _layernorm(x, axis=-1, eps=1e-05):
    m = x.mean(dim=axis, keepdim=True)
    v = x.var(dim=axis, keepdim=True, unbiased=False)
    return (x - m) / torch.sqrt(v + eps)

def _scatter_add(tgt, idx, src, axis=0):
    return tgt.clone().index_add_(axis, idx, src)

def _segment_sum(src, seg, n):
    out = torch.zeros((n,) + src.shape[1:], dtype=src.dtype)
    return out.index_add_(0, seg, src)

def _pad(x, pw):
    flat = tuple((v for pair in reversed(pw) for v in pair))
    return torch.nn.functional.pad(x, flat)
kernel_name = 'standalone__detection_seg_detr_decoder__vision'

def setup_inputs():

    _w = lambda a: (lambda t: t.to(torch.bfloat16) if t.is_floating_point() else t)(torch.as_tensor(a))
    H = W = 384 // 2 * 2
    C = 384
    Nq = 32
    return {'q': _w((lambda *s: torch.randn(*s, dtype=torch.bfloat16) * 0.05)(1, Nq, C)), 'feat_hi': _w((lambda *s: torch.randn(*s, dtype=torch.bfloat16) * 0.1)(1, H, W, C)), 'feat_lo': _w((lambda *s: torch.randn(*s, dtype=torch.bfloat16) * 0.1)(1, H // 2, W // 2, C)), 'lat_hi': _w((lambda *s: torch.randn(*s, dtype=torch.bfloat16) * 0.1)(C, C)), 'lat_lo': _w((lambda *s: torch.randn(*s, dtype=torch.bfloat16) * 0.1)(C, C)), 'wq': _w((lambda *s: torch.randn(*s, dtype=torch.bfloat16) * 0.1)(C, C)), 'wkv': _w((lambda *s: torch.randn(*s, dtype=torch.bfloat16) * 0.1)(C, 2 * C)), 'wo': _w((lambda *s: torch.randn(*s, dtype=torch.bfloat16) * 0.05)(C, C)), 'w1': _w((lambda *s: torch.randn(*s, dtype=torch.bfloat16) * 0.05)(C, 4 * C)), 'w2': _w((lambda *s: torch.randn(*s, dtype=torch.bfloat16) * 0.05)(4 * C, C))}

def reference(q, feat_hi, feat_lo, lat_hi, lat_lo, wq, wkv, wo, w1, w2):
    B, Nq, C = q.shape
    _, H, W, _ = feat_hi.shape
    lo = feat_lo @ lat_lo
    up = (lambda x, n, axis: torch.repeat_interleave(x, n, dim=axis))((lambda x, n, axis: torch.repeat_interleave(x, n, dim=axis))(lo, 2, axis=1), 2, axis=2)
    fused = feat_hi @ lat_hi + up
    mem = fused.reshape(B, H * W, C)
    qn = _layernorm(q, axis=-1)
    Q = qn @ wq
    KV = mem @ wkv
    K, V = (KV[..., :C].clone(), KV[..., C:].clone())
    scale = C ** (-0.5)
    logits = torch.einsum('bqc,bkc->bqk', Q, K) * scale
    P = _softmax(logits, axis=-1)
    O = torch.einsum('bqk,bkc->bqc', P, V)
    h = q + O @ wo
    hn = _layernorm(h, axis=-1)
    return h + _gelu(hn @ w1) @ w2
```

```cpp
#include <cuda_runtime.h>
#include <cuda_bf16.h>
#include <cuda.h>
#include <stdint.h>

namespace {

constexpr int C = 384;
constexpr int NUNITS = 2304;
constexpr int MAXCTA = 132;
constexpr int NTAIL = 96;
constexpr int NTHREADS = 256;
constexpr uint32_t HI_BYTES = 49152, LO_BYTES = 12288, STAGE_BYTES = 61440;
constexpr uint32_t OFF_PH = 3 * STAGE_BYTES;
constexpr uint32_t OFF_WS = OFF_PH + 21504;
constexpr uint32_t OFF_BAR = OFF_WS + 24576;
constexpr uint32_t SMEM_BYTES = OFF_BAR + 1024 + 1024;
constexpr int SPIN_LIMIT = 1 << 20;

struct Scratch {
    uint4 part[MAXCTA * 4 * 24 * 32];
    uint4 qf[4 * 24 * 32];
    uint4 h[32 * 96];
    uint4 a[32 * 96];
    uint4 g[32 * 192];
    uint4 q1[32 * 48], qk[32 * 48], m[32 * 48], o[32 * 48];
    uint2 ml[MAXCTA * 32];
};
__device__ unsigned g_ctr[2];
__device__ Scratch g_x;
__device__ unsigned g_epoch;
#define CK_DECL
#define CK(i)
#define CK_OUT(o)
#define STAMP(i)

__device__ __forceinline__ uint32_t smem_u32(const void* p) { return (uint32_t)__cvta_generic_to_shared(p); }
__device__ __forceinline__ void mbar_init(uint32_t bar, uint32_t cnt) { asm volatile("mbarrier.init.shared::cta.b64 [%0], %1;" :: "r"(bar), "r"(cnt) : "memory"); }
__device__ __forceinline__ void mbar_expect(uint32_t bar, uint32_t bytes) { asm volatile("mbarrier.arrive.expect_tx.shared::cta.b64 _, [%0], %1;" :: "r"(bar), "r"(bytes) : "memory"); }
__device__ __forceinline__ void mbar_wait(uint32_t bar, uint32_t parity) {
    uint32_t ok = 0;
    for (int it = 0; it < SPIN_LIMIT && !ok; ++it)
        asm volatile("{\n.reg .pred p;\nmbarrier.try_wait.parity.shared::cta.b64 p, [%1], %2;\nselp.u32 %0, 1, 0, p;\n}\n" : "=r"(ok) : "r"(bar), "r"(parity) : "memory");
}
__device__ __forceinline__ void bar_sync(int id, int n) { asm volatile("bar.sync %0, %1;" :: "r"(id), "r"(n) : "memory"); }
__device__ __forceinline__ void bar_arrive(int id, int n) { asm volatile("bar.arrive %0, %1;" :: "r"(id), "r"(n) : "memory"); }
__device__ __forceinline__ void tma2d(uint32_t dst, const CUtensorMap* m, int x, int y, uint32_t bar) {
    asm volatile("cp.async.bulk.tensor.2d.shared::cluster.global.mbarrier::complete_tx::bytes [%0], [%1, {%3, %4}], [%2];"
                 :: "r"(dst), "l"(m), "r"(bar), "r"(x), "r"(y) : "memory");
}
__device__ __forceinline__ void load_piece(uint32_t dst, const CUtensorMap* mh, const CUtensorMap* ml, int u, int p, uint32_t bar, uint64_t pol) {
    const int j = u / 12, xb = (u - j * 12) * 16;
    mbar_expect(bar, 20480);
    asm volatile("cp.async.bulk.tensor.5d.shared::cluster.global.mbarrier::complete_tx::bytes.L2::cache_hint [%0], [%1, {%3, %4, %3, %5, %7}], [%2], %6;"
                 :: "r"(dst + p * 16384), "l"(mh), "r"(bar), "r"(0), "r"(xb), "r"(2 * j), "l"(pol), "r"(2 * p) : "memory");
    asm volatile("cp.async.bulk.tensor.3d.shared::cluster.global.mbarrier::complete_tx::bytes.L2::cache_hint [%0], [%1, {%3, %4, %6}], [%2], %5;"
                 :: "r"(dst + HI_BYTES + p * 4096), "l"(ml), "r"(bar), "r"(0), "r"(u * 16), "l"(pol), "r"(2 * p) : "memory");
}
__device__ __forceinline__ void load_piece_if(int go, uint32_t dst, const CUtensorMap* mh, const CUtensorMap* ml, int u, int p, uint32_t bar, uint64_t pol) {
    const int j = u / 12, xb = (u - j * 12) * 16;
    asm volatile("{\n.reg .pred q;\nsetp.ne.b32 q, %11, 0;\n"
                 "@q mbarrier.arrive.expect_tx.shared::cta.b64 _, [%2], 20480;\n"
                 "@q cp.async.bulk.tensor.5d.shared::cluster.global.mbarrier::complete_tx::bytes.L2::cache_hint [%0], [%1, {%3, %4, %3, %5, %7}], [%2], %6;\n"
                 "@q cp.async.bulk.tensor.3d.shared::cluster.global.mbarrier::complete_tx::bytes.L2::cache_hint [%8], [%9, {%3, %10, %7}], [%2], %6;\n}\n"
                 :: "r"(dst + p * 16384), "l"(mh), "r"(bar), "r"(0), "r"(xb), "r"(2 * j), "l"(pol), "r"(2 * p),
                    "r"(dst + HI_BYTES + p * 4096), "l"(ml), "r"(u * 16), "r"(go) : "memory");
}
__device__ __forceinline__ uint64_t make_desc(uint32_t addr, uint32_t lbo, uint32_t sbo) {
    return (uint64_t)((addr & 0x3FFFF) >> 4) | ((uint64_t)(lbo >> 4) << 16) | ((uint64_t)(sbo >> 4) << 32) | (1ull << 62);
}
__device__ __forceinline__ void wg_fence() { asm volatile("wgmma.fence.sync.aligned;" ::: "memory"); }
__device__ __forceinline__ void wg_commit() { asm volatile("wgmma.commit_group.sync.aligned;" ::: "memory"); }
__device__ __forceinline__ void wg_wait2() { asm volatile("wgmma.wait_group.sync.aligned 2;" ::: "memory"); }
__device__ __forceinline__ void wg_wait1() { asm volatile("wgmma.wait_group.sync.aligned 1;" ::: "memory"); }
__device__ __forceinline__ void wg_wait0() { asm volatile("wgmma.wait_group.sync.aligned 0;" ::: "memory"); }
template <int N> __device__ __forceinline__ void reg_fence(float (&d)[N]) {
#pragma unroll
    for (int i = 0; i < N; ++i) asm volatile("" : "+f"(d[i]) :: "memory");
}
__device__ __forceinline__ uint32_t pack2(float lo, float hi) { uint32_t r; asm("cvt.rn.bf16x2.f32 %0, %1, %2;" : "=r"(r) : "f"(hi), "f"(lo)); return r; }
__device__ __forceinline__ float bf_lo(uint32_t v) { return __uint_as_float(v << 16); }
__device__ __forceinline__ float bf_hi(uint32_t v) { return __uint_as_float(v & 0xFFFF0000u); }
__device__ __forceinline__ float ex2(float x) { float r; asm("ex2.approx.ftz.f32 %0, %1;" : "=f"(r) : "f"(x)); return r; }
__device__ __forceinline__ uint32_t tagw(uint32_t v, uint32_t tag) { return (v & ~1u) | tag; }
__device__ __forceinline__ void st_ll(uint4* p, uint4 v) { asm volatile("st.relaxed.gpu.global.v4.u32 [%0], {%1, %2, %3, %4};" :: "l"(p), "r"(v.x), "r"(v.y), "r"(v.z), "r"(v.w) : "memory"); }
__device__ __forceinline__ void st_ll(uint2* p, uint2 v) { asm volatile("st.relaxed.gpu.global.v2.u32 [%0], {%1, %2};" :: "l"(p), "r"(v.x), "r"(v.y) : "memory"); }
__device__ __forceinline__ void ld_ll(uint4& v, const uint4* p) { asm volatile("ld.relaxed.gpu.global.v4.u32 {%0, %1, %2, %3}, [%4];" : "=r"(v.x), "=r"(v.y), "=r"(v.z), "=r"(v.w) : "l"(p) : "memory"); }
__device__ __forceinline__ void ld_ll(uint2& v, const uint2* p) { asm volatile("ld.relaxed.gpu.global.v2.u32 {%0, %1}, [%2];" : "=r"(v.x), "=r"(v.y) : "l"(p) : "memory"); }
template <int N, bool TWO, typename V> __device__ __forceinline__ void poll(V (&v)[N], const V* p, int stride, uint32_t tag) {
    for (int it = 0; it < SPIN_LIMIT; ++it) {
#pragma unroll
        for (int i = 0; i < N; ++i) ld_ll(v[i], p + i * stride);
        uint32_t bad = 0;
#pragma unroll
        for (int i = 0; i < N; ++i) {
            bad |= v[i].x ^ tag;
            if constexpr (TWO) bad |= v[i].z ^ tag;
        }
        if (!__any_sync(0xffffffffu, bad & 1)) break;
    }
}
__device__ __forceinline__ void mma16816(float (&c)[4], uint32_t a0, uint32_t a1, uint32_t a2, uint32_t a3, uint32_t b0, uint32_t b1) {
    asm volatile("mma.sync.aligned.m16n8k16.row.col.f32.bf16.bf16.f32 {%0, %1, %2, %3}, {%4, %5, %6, %7}, {%8, %9}, {%0, %1, %2, %3};"
                 : "+f"(c[0]), "+f"(c[1]), "+f"(c[2]), "+f"(c[3]) : "r"(a0), "r"(a1), "r"(a2), "r"(a3), "r"(b0), "r"(b1));
}
__device__ __forceinline__ void ldsm4t(uint32_t (&a)[4], uint32_t addr) {
    asm volatile("ldmatrix.sync.aligned.m8n8.x4.trans.shared.b16 {%0, %1, %2, %3}, [%4];" : "=r"(a[0]), "=r"(a[1]), "=r"(a[2]), "=r"(a[3]) : "r"(addr) : "memory");
}
__device__ __forceinline__ void ld_w16(uint32_t (&a)[8], uint32_t wbase, int k0, int lane) {
    const int k = (lane & 7) + ((lane >> 4) << 3);
    const uint32_t p = wbase + (k0 + k) * 32 + ((((lane >> 3) ^ (k >> 2)) & 1) << 4);
    ldsm4t(*reinterpret_cast<uint32_t(*)[4]>(&a[0]), p);
    ldsm4t(*reinterpret_cast<uint32_t(*)[4]>(&a[4]), p + 512);
}
__device__ __forceinline__ void mma32(float (&c)[4], const uint32_t (&a)[8], const uint2* v) {
    mma16816(c, a[0], a[1], a[2], a[3], v[0].x, v[0].y);
    mma16816(c, a[4], a[5], a[6], a[7], v[1].x, v[1].y);
}
__device__ __forceinline__ void mma96(float (&c)[4], const uint32_t (&a0)[8], const uint32_t (&a1)[8], const uint32_t (&a2)[8], const uint2* v) {
    float d[4] = {0.f, 0.f, 0.f, 0.f}, e[4] = {0.f, 0.f, 0.f, 0.f};
    c[0] = c[1] = c[2] = c[3] = 0.f;
    mma32(c, a0, v); mma32(d, a1, v + 2); mma32(e, a2, v + 4);
#pragma unroll
    for (int j = 0; j < 4; ++j) c[j] += d[j] + e[j];
}
__device__ __forceinline__ void st_part(uint4* p, uint4 v) { asm volatile("st.global.v4.u32 [%0], {%1, %2, %3, %4};" :: "l"(p), "r"(v.x), "r"(v.y), "r"(v.z), "r"(v.w) : "memory"); }
template <int PITCH> __device__ __forceinline__ void red_put(float* red, int part, int lane, int n0, const float (&c)[4]) {
    float* p = red + (part * 8 + 2 * (lane & 3)) * PITCH + n0 + (lane >> 2);
    p[0] = c[0]; p[PITCH] = c[1]; p[8] = c[2]; p[PITCH + 8] = c[3];
}
template <int PITCH, int NP> __device__ __forceinline__ float4 red_get(const float* red, int lane, int n0) {
    const float* p = red + (lane >> 2) * PITCH + n0 + 4 * (lane & 3);
    float4 s = *reinterpret_cast<const float4*>(p);
#pragma unroll
    for (int w = 1; w < NP; ++w) {
        const float4 x = *reinterpret_cast<const float4*>(p + w * 8 * PITCH);
        s.x += x.x; s.y += x.y; s.z += x.z; s.w += x.w;
    }
    return s;
}
template <int PITCH, int NP> __device__ __forceinline__ float4 red_getn(const float* red, int lane, int n0) {
    const float* p = red + (lane >> 2) * PITCH + n0 + 2 * (lane & 3);
    float4 s = make_float4(0.f, 0.f, 0.f, 0.f);
#pragma unroll
    for (int w = 0; w < NP; ++w) {
        const float2 x = *reinterpret_cast<const float2*>(p + w * 8 * PITCH), y = *reinterpret_cast<const float2*>(p + w * 8 * PITCH + 8);
        s.x += x.x; s.y += x.y; s.z += y.x; s.w += y.y;
    }
    return s;
}
__device__ __forceinline__ void st_bf4(uint4* base, int idx8, const float4& s, uint32_t tag) {
    st_ll(reinterpret_cast<uint2*>(base) + idx8, make_uint2(tagw(pack2(s.x, s.y), tag), pack2(s.z, s.w)));
}
__device__ __forceinline__ void layernorm_frag(const float (&x)[24], uint2 (&b)[6], float2* st, int w4, int lane, int bar) {
    float s = 0.f;
#pragma unroll
    for (int i = 0; i < 24; i += 4) s += (x[i] + x[i + 1]) + (x[i + 2] + x[i + 3]);
    s += __shfl_xor_sync(0xffffffffu, s, 1); s += __shfl_xor_sync(0xffffffffu, s, 2);
    const float mw = s * (1.f / 96);
    float v0 = 0.f, v1 = 0.f;
#pragma unroll
    for (int i = 0; i < 24; i += 2) { v0 = fmaf(x[i] - mw, x[i] - mw, v0); v1 = fmaf(x[i + 1] - mw, x[i + 1] - mw, v1); }
    float v = v0 + v1;
    v += __shfl_xor_sync(0xffffffffu, v, 1); v += __shfl_xor_sync(0xffffffffu, v, 2);
    if ((lane & 3) == 0) st[(lane >> 2) * 4 + w4] = make_float2(mw, v);
    bar_sync(bar, 128);
    const float4 u0 = *reinterpret_cast<const float4*>(st + (lane >> 2) * 4), u1 = *reinterpret_cast<const float4*>(st + (lane >> 2) * 4 + 2);
    const float mean = ((u0.x + u0.z) + (u1.x + u1.z)) * 0.25f;
    const float d0 = u0.x - mean, d1 = u0.z - mean, d2 = u1.x - mean, d3 = u1.z - mean;
    const float var = ((u0.y + u0.w) + (u1.y + u1.w)) * (1.f / C) + ((d0 * d0 + d1 * d1) + (d2 * d2 + d3 * d3)) * 0.25f;
    const float rs = rsqrtf(var + 1e-5f), sh = -mean * rs;
#pragma unroll
    for (int j = 0; j < 6; ++j)
        b[j] = make_uint2(pack2(fmaf(x[4 * j], rs, sh), fmaf(x[4 * j + 1], rs, sh)), pack2(fmaf(x[4 * j + 2], rs, sh), fmaf(x[4 * j + 3], rs, sh)));
}
__device__ __forceinline__ float gelu_tanh(float x) {
    const float k = -2.f * 0.7978845608028654f * 1.4426950408889634f;
    return __fdividef(x, 1.f + ex2(x * fmaf(x * x, 0.044715f * k, k)));
}
__device__ __forceinline__ uint32_t hmul_bf2(uint32_t a, uint32_t b) { uint32_t r; asm("mul.rn.bf16x2 %0, %1, %2;" : "=r"(r) : "r"(a), "r"(b)); return r; }
#define NPREF 2
#define FEAT_PROMO CU_TENSOR_MAP_L2_PROMOTION_L2_256B
__device__ __forceinline__ void wgmma_n64(float (&d)[32], uint32_t a0, uint32_t a1, uint32_t a2, uint32_t a3, uint64_t desc, int scale_d) {
    asm volatile("{\n.reg .pred p;\nsetp.ne.b32 p, %37, 0;\n"
        "wgmma.mma_async.sync.aligned.m64n64k16.f32.bf16.bf16 "
        "{%0, %1, %2, %3, %4, %5, %6, %7, %8, %9, %10, %11, %12, %13, %14, %15, "
        "%16, %17, %18, %19, %20, %21, %22, %23, %24, %25, %26, %27, %28, %29, %30, %31}, "
        "{%32, %33, %34, %35}, %36, p, 1, 1, 0;\n}\n"
        : "+f"(d[0]), "+f"(d[1]), "+f"(d[2]), "+f"(d[3]), "+f"(d[4]), "+f"(d[5]), "+f"(d[6]), "+f"(d[7]),
          "+f"(d[8]), "+f"(d[9]), "+f"(d[10]), "+f"(d[11]), "+f"(d[12]), "+f"(d[13]), "+f"(d[14]), "+f"(d[15]),
          "+f"(d[16]), "+f"(d[17]), "+f"(d[18]), "+f"(d[19]), "+f"(d[20]), "+f"(d[21]), "+f"(d[22]), "+f"(d[23]),
          "+f"(d[24]), "+f"(d[25]), "+f"(d[26]), "+f"(d[27]), "+f"(d[28]), "+f"(d[29]), "+f"(d[30]), "+f"(d[31])
        : "r"(a0), "r"(a1), "r"(a2), "r"(a3), "l"(desc), "r"(scale_d));
}
__device__ __forceinline__ void wgmma_n16(float (&d)[8], uint32_t a0, uint32_t a1, uint32_t a2, uint32_t a3, uint64_t desc, int scale_d) {
    asm volatile("{\n.reg .pred p;\nsetp.ne.b32 p, %13, 0;\n"
        "wgmma.mma_async.sync.aligned.m64n16k16.f32.bf16.bf16 "
        "{%0, %1, %2, %3, %4, %5, %6, %7}, "
        "{%8, %9, %10, %11}, %12, p, 1, 1, 0;\n}\n"
        : "+f"(d[0]), "+f"(d[1]), "+f"(d[2]), "+f"(d[3]), "+f"(d[4]), "+f"(d[5]), "+f"(d[6]), "+f"(d[7])
        : "r"(a0), "r"(a1), "r"(a2), "r"(a3), "l"(desc), "r"(scale_d));
}
__device__ __forceinline__ void wgmma_n128t(float (&d)[64], uint32_t a0, uint32_t a1, uint32_t a2, uint32_t a3, uint64_t desc, int scale_d) {
    asm volatile("{\n.reg .pred p;\nsetp.ne.b32 p, %69, 0;\n"
        "wgmma.mma_async.sync.aligned.m64n128k16.f32.bf16.bf16 "
        "{%0, %1, %2, %3, %4, %5, %6, %7, %8, %9, %10, %11, %12, %13, %14, %15, "
        "%16, %17, %18, %19, %20, %21, %22, %23, %24, %25, %26, %27, %28, %29, %30, %31, "
        "%32, %33, %34, %35, %36, %37, %38, %39, %40, %41, %42, %43, %44, %45, %46, %47, "
        "%48, %49, %50, %51, %52, %53, %54, %55, %56, %57, %58, %59, %60, %61, %62, %63}, "
        "{%64, %65, %66, %67}, %68, p, 1, 1, 1;\n}\n"
        : "+f"(d[0]), "+f"(d[1]), "+f"(d[2]), "+f"(d[3]), "+f"(d[4]), "+f"(d[5]), "+f"(d[6]), "+f"(d[7]),
          "+f"(d[8]), "+f"(d[9]), "+f"(d[10]), "+f"(d[11]), "+f"(d[12]), "+f"(d[13]), "+f"(d[14]), "+f"(d[15]),
          "+f"(d[16]), "+f"(d[17]), "+f"(d[18]), "+f"(d[19]), "+f"(d[20]), "+f"(d[21]), "+f"(d[22]), "+f"(d[23]),
          "+f"(d[24]), "+f"(d[25]), "+f"(d[26]), "+f"(d[27]), "+f"(d[28]), "+f"(d[29]), "+f"(d[30]), "+f"(d[31]),
          "+f"(d[32]), "+f"(d[33]), "+f"(d[34]), "+f"(d[35]), "+f"(d[36]), "+f"(d[37]), "+f"(d[38]), "+f"(d[39]),
          "+f"(d[40]), "+f"(d[41]), "+f"(d[42]), "+f"(d[43]), "+f"(d[44]), "+f"(d[45]), "+f"(d[46]), "+f"(d[47]),
          "+f"(d[48]), "+f"(d[49]), "+f"(d[50]), "+f"(d[51]), "+f"(d[52]), "+f"(d[53]), "+f"(d[54]), "+f"(d[55]),
          "+f"(d[56]), "+f"(d[57]), "+f"(d[58]), "+f"(d[59]), "+f"(d[60]), "+f"(d[61]), "+f"(d[62]), "+f"(d[63])
        : "r"(a0), "r"(a1), "r"(a2), "r"(a3), "l"(desc), "r"(scale_d));
}
#define GATE (!tail)
#define PACEN 2
#define PACE 1
struct Maps { CUtensorMap hi, lo, wq, lath, latl, wkv, wo, w1, w2; };

__global__ void __launch_bounds__(NTHREADS, 1)
detr_kernel(const __grid_constant__ Maps mp, const __nv_bfloat16* __restrict__ q, const __nv_bfloat16* __restrict__ fhi,
            const __nv_bfloat16* __restrict__ flo, const __nv_bfloat16* __restrict__ lath, const __nv_bfloat16* __restrict__ latl,
            const __nv_bfloat16* __restrict__ wkv, __nv_bfloat16* __restrict__ out, int ncta) {
    extern __shared__ uint8_t smem_raw[];
    const uint32_t sraw = smem_u32(smem_raw);
    const uint32_t sb = (sraw + 1023u) & ~1023u;
    uint8_t* sp = smem_raw + (sb - sraw);
    const int tid = threadIdx.x, warp = tid >> 5, lane = tid & 31, g = lane >> 2, t = lane & 3;
    const int cta = blockIdx.x;
    const bool tail = cta < NTAIL;
    const int rg = cta / 24, sl = cta - rg * 24;
    const uint32_t barF = sb + OFF_BAR, barW = barF + 72;
    float* stat = reinterpret_cast<float*>(sp + OFF_BAR + 256);
    volatile int* s_nu = reinterpret_cast<volatile int*>(sp + OFF_BAR + 128);
    volatile int* s_go = s_nu + 1;
    const int w4 = warp & 3;
    STAMP(0);
    uint32_t tag;
    asm volatile("ld.relaxed.gpu.global.u32 %0, [%1];" : "=r"(tag) : "l"(&g_epoch) : "memory");
    uint64_t pol;
    asm volatile("createpolicy.fractional.L2::evict_first.b64 %0, 1.0;" : "=l"(pol));
    uint32_t qv[12];
    uint4 wk[3][2], la[3][2][2];
    if (warp >= 4) {
        if (tid == 128) {
            for (int i = 0; i < 4; ++i) mbar_init(barW + 8 * i, 1);
            for (int i = 0; i < 9; ++i) mbar_init(barF + 8 * i, 1);
            asm volatile("fence.mbarrier_init.release.cluster;" ::: "memory");
            *s_nu = 1 << 30; *s_go = 0;
            if (tail) {
                mbar_expect(barW, 12288);
                tma2d(sb + OFF_WS, &mp.wq, sl * 16, 0, barW);
                tma2d(sb + OFF_WS + 6144, &mp.wq, sl * 16, 192, barW);
            }
            for (int k = 0; k < (tail ? PACE : PACEN); ++k) load_piece(sb, &mp.hi, &mp.lo, cta, k, barF + 8 * k, pol);
        }
        __syncwarp();
    } else if (tail) {
        const int kc = w4 * 96 + 8 * t;
#pragma unroll
        for (int j = 0; j < 12; ++j) qv[j] = __ldg(reinterpret_cast<const uint32_t*>(q + (rg * 8 + g) * C + w4 * 96 + 2 * t + j * 8));
#pragma unroll
        for (int j = 0; j < 3; ++j)
#pragma unroll
            for (int r = 0; r < 2; ++r) {
                const int n = sl * 16 + g + r * 8;
                wk[j][r] = __ldg(reinterpret_cast<const uint4*>(wkv + n * 2 * C + kc + j * 32));
                la[j][0][r] = __ldg(reinterpret_cast<const uint4*>(lath + n * C + kc + j * 32));
                la[j][1][r] = __ldg(reinterpret_cast<const uint4*>(latl + n * C + kc + j * 32));
            }
    }
    const int xi = (rg * 24 + sl) * 32 + lane;
    const int x8 = xi;
    const int lv = (t >> 1) * 16 + g * 2 + (t & 1);
    const int xr = (rg * 12 + w4 * 3) * 32 + lv;
    const int xq = (rg * 8 + g) * 192 + sl * 8 + t;
    if (warp >= 4) {
        const uint2 z2 = make_uint2(tag, 0u);
        const uint4 z4 = make_uint4(tag, 0u, 0u, 0u);
        if (tail) {
            if (w4 == 1) {
                st_ll(reinterpret_cast<uint2*>(g_x.q1) + x8, z2); st_ll(reinterpret_cast<uint2*>(g_x.qk) + x8, z2); st_ll(&g_x.qf[xi], z4);
                st_ll(reinterpret_cast<uint2*>(g_x.m) + x8, z2); st_ll(reinterpret_cast<uint2*>(g_x.o) + x8, z2); st_ll(reinterpret_cast<uint2*>(g_x.h) + x8, z2);
            }
            if (w4 >= 2) st_ll(reinterpret_cast<uint2*>(g_x.a) + (rg * 48 + sl * 2 + w4 - 2) * 32 + lane, z2);
            st_ll(reinterpret_cast<uint2*>(g_x.g) + (rg * 96 + sl * 4 + w4) * 32 + lane, z2);
        }
        if (t == 0) st_ll(&g_x.ml[cta * 32 + w4 * 8 + g], z2);
        if (cta == ncta - 1 && tid == 192) g_ctr[tag] = 0;
        bar_arrive(0, 256);
    } else if (!tail) {
        bar_sync(0, 256);
    }
    tag ^= 1;
    STAMP(14);

    if (tail && warp < 4) {
        float* red = reinterpret_cast<float*>(sp + OFF_PH);
        float x[24]; uint4 v[3]; uint2 b[6];
#pragma unroll
        for (int j = 0; j < 12; ++j) { x[2 * j] = bf_lo(qv[j]); x[2 * j + 1] = bf_hi(qv[j]); }
        layernorm_frag(x, b, reinterpret_cast<float2*>(stat), w4, lane, 9);
        STAMP(15);
        bar_sync(0, 256);
        mbar_wait(barW, 0);
        STAMP(13);
        float c[4] = {0.f, 0.f, 0.f, 0.f}, c2[4] = {0.f, 0.f, 0.f, 0.f};
        {
            uint32_t a[3][8];
#pragma unroll
            for (int j = 0; j < 3; ++j) ld_w16(a[j], sb + OFF_WS, w4 * 96 + j * 32, lane);
            mma96(c, a[0], a[1], a[2], b);
        }
        red_put<20>(red, w4, lane, 0, c);
        bar_sync(9, 128);
        if (warp == 0) st_bf4(g_x.q1, x8, red_get<20, 4>(red, lane, 0), tag);
        STAMP(1);
        poll<3, true>(v, &g_x.q1[xr], 32, tag);
        c[0] = c[1] = c[2] = c[3] = 0.f;
#pragma unroll
        for (int j = 0; j < 3; ++j) {
            mma16816(c, wk[j][0].x, wk[j][1].x, wk[j][0].y, wk[j][1].y, v[j].x, v[j].y);
            mma16816(c2, wk[j][0].z, wk[j][1].z, wk[j][0].w, wk[j][1].w, v[j].z, v[j].w);
        }
#pragma unroll
        for (int j = 0; j < 4; ++j) c[j] += c2[j];
        red_put<20>(red + 640, w4, lane, 0, c);
        bar_sync(9, 128);
        if (warp == 0) st_bf4(g_x.qk, x8, red_get<20, 4>(red + 640, lane, 0), tag);
        STAMP(2);
        poll<3, true>(v, &g_x.qk[xr], 32, tag);
        c[0] = c[1] = c[2] = c[3] = 0.f; c2[0] = c2[1] = c2[2] = c2[3] = 0.f;
#pragma unroll
        for (int j = 0; j < 3; ++j) {
            mma16816(c, la[j][0][0].x, la[j][0][1].x, la[j][0][0].y, la[j][0][1].y, v[j].x, v[j].y);
            mma16816(c2, la[j][1][0].x, la[j][1][1].x, la[j][1][0].y, la[j][1][1].y, v[j].x, v[j].y);
            mma16816(c, la[j][0][0].z, la[j][0][1].z, la[j][0][0].w, la[j][0][1].w, v[j].z, v[j].w);
            mma16816(c2, la[j][1][0].z, la[j][1][1].z, la[j][1][0].w, la[j][1][1].w, v[j].z, v[j].w);
        }
        red_put<40>(red + 1280, w4, lane, 0, c);
        red_put<40>(red + 1280, w4, lane, 16, c2);
        bar_sync(9, 128);
        if (warp == 0) {
            float2 s[4];
#pragma unroll
            for (int r = 0; r < 4; ++r) {
                const float* p = red + 1280 + g * 40 + (r & 1) * 16 + (r >> 1) * 8 + 2 * t;
                s[r] = *reinterpret_cast<const float2*>(p);
#pragma unroll
                for (int w = 1; w < 4; ++w) { const float2 y = *reinterpret_cast<const float2*>(p + w * 320); s[r].x += y.x; s[r].y += y.y; }
            }
            const float sc = 0.05103103630798288f * 1.4426950408889634f;
            st_ll(&g_x.qf[xi], make_uint4(tagw(pack2(s[0].x * sc, s[0].y * sc), tag), pack2(s[1].x * sc, s[1].y * sc),
                                          pack2(s[2].x * sc, s[2].y * sc), pack2(s[3].x * sc, s[3].y * sc)));
        }
        bar_sync(9, 128);
        STAMP(3);
    }

    uint4* ph = reinterpret_cast<uint4*>(sp + OFF_PH);
    if (warp < 4) {
        uint4 qa[24];
        {
            const uint4* pq = &g_x.qf[warp * 24 * 32 + lane];
            uint32_t done = 0;
            if (GATE) {
                for (int it = 0; it < SPIN_LIMIT; ++it) {
                    ld_ll(qa[0], pq);
                    if (!__any_sync(0xffffffffu, (qa[0].x ^ tag) & 1)) break;
                }
                done = 1;
            }
            for (int it = 0; it < SPIN_LIMIT && done != 0xffffffu; ++it) {
                uint32_t ok = 0;
#pragma unroll
                for (int i = 0; i < 24; ++i) if (!(done >> i & 1)) ld_ll(qa[i], pq + i * 32);
#pragma unroll
                for (int i = 0; i < 24; ++i) ok |= (qa[i].x & 1) << i;
                done = __reduce_and_sync(0xffffffffu, tag ? ok : ok ^ 0xffffffu);
            }
        }
        STAMP(4);
        if (tid == 0) *s_go = 1;
        float mrun = -INFINITY, lrun = 0.f;
        CK_DECL;
        int st = 0, ph_par = 0;
        for (int i = 0;; ++i) {
            const uint32_t base = sb + st * STAGE_BYTES;
            mbar_wait(barF + 24 * st, ph_par);
            if (i == *s_nu) break;
            CK(0);
            float sh[32], slo[8];
            const uint64_t dh = make_desc(base, 16, 1024), dl = make_desc(base + HI_BYTES, 16, 1024);
            wg_fence();
#pragma unroll
            for (int k = 0; k < 24; ++k) {
                if (k == 8 || k == 16) { wg_commit(); mbar_wait(barF + 24 * st + k, ph_par); wg_fence(); }
                wgmma_n64(sh, qa[k].x, qa[k].y, qa[k].z, qa[k].w, dh + ((k >> 2) * 8192 + (k & 3) * 32) / 16, k);
                wgmma_n16(slo, qa[k].x, qa[k].y, qa[k].z, qa[k].w, dl + ((k >> 2) * 2048 + (k & 3) * 32) / 16, k);
            }
            wg_commit();
            wg_wait0();
            reg_fence(sh); reg_fence(slo);
            CK(1);
            float s[16];
#pragma unroll
            for (int j = 0; j < 8; ++j) { s[2 * j] = sh[4 * j] + slo[4 * (j & 1) + 2]; s[2 * j + 1] = sh[4 * j + 1] + slo[4 * (j & 1) + 3]; }
            float mx = s[0];
#pragma unroll
            for (int j = 1; j < 16; ++j) mx = fmaxf(mx, s[j]);
            mx = fmaxf(mx, __shfl_xor_sync(0xffffffffu, mx, 1));
            mx = fmaxf(mx, __shfl_xor_sync(0xffffffffu, mx, 2));
            const float mnew = fmaxf(mrun, mx);
            const float alpha = ex2(mrun - mnew);
            mrun = mnew;
#pragma unroll
            for (int j = 0; j < 16; ++j) s[j] = ex2(s[j] - mnew);
            float pl[4];
#pragma unroll
            for (int j = 0; j < 4; ++j) pl[j] = (s[j] + s[4 + j]) + (s[8 + j] + s[12 + j]);
            lrun = lrun * alpha + ((pl[0] + pl[1]) + (pl[2] + pl[3]));
            CK(2);
            if (i >= 2) bar_sync(4 + (i & 1), 256);
            uint4* dst = ph + (i & 1) * 672 + tid;
#pragma unroll
            for (int j = 0; j < 4; ++j) dst[j * 128] = make_uint4(pack2(s[4 * j], s[4 * j + 1]), 0u, pack2(s[4 * j + 2], s[4 * j + 3]), 0u);
            dst[512] = make_uint4(0u, pack2(pl[0], pl[1]), 0u, pack2(pl[2], pl[3]));
            reinterpret_cast<float*>(ph + (i & 1) * 672 + 640)[tid] = alpha;
            bar_arrive(2 + (i & 1), 256);
            CK(3);
            if (++st == 3) { st = 0; ph_par ^= 1; }
        }
        lrun += __shfl_xor_sync(0xffffffffu, lrun, 1);
        lrun += __shfl_xor_sync(0xffffffffu, lrun, 2);
        if (t == 0) reinterpret_cast<uint2*>(stat + 128)[warp * 8 + g] = make_uint2(tagw(__float_as_uint(lrun), tag), __float_as_uint(mrun));
        bar_sync(7, 256);
        { const int nu = *s_nu; STAMP(5); CK_OUT(0); }
    } else {
        float o0[64], o1[64], o2[64];
#pragma unroll
        for (int j = 0; j < 64; ++j) { o0[j] = 0.f; o1[j] = 0.f; o2[j] = 0.f; }
        int pend = 0;
        if (tid == 128) {
            const int pace = tail ? PACE : PACEN;
            int k = pace;
            for (int it = 0; k < 9 && it < SPIN_LIMIT; ++it) {
                uint32_t ok;
                asm volatile("{\n.reg .pred p;\nmbarrier.test_wait.parity.shared::cta.b64 p, [%1], 0;\nselp.u32 %0, 1, 0, p;\n}\n" : "=r"(ok) : "r"(barF + 8 * (k - pace)) : "memory");
                if (ok || *s_go) { load_piece(sb + (k / 3) * STAGE_BYTES, &mp.hi, &mp.lo, cta + (k / 3) * ncta, k % 3, barF + 8 * k, pol); ++k; }
            }
            pend = atomicAdd(&g_ctr[tag], 1);
        }
        __syncwarp();
        uint4* dst = &g_x.part[(cta * 4 + w4) * 24 * 32 + lane];
#define PART(o, r) make_uint4(tagw(pack2(o[16 * s + r], o[16 * s + r + 1]), tag), pack2(o[16 * s + 4 + r], o[16 * s + 5 + r]), \
                              pack2(o[16 * s + 8 + r], o[16 * s + 9 + r]), pack2(o[16 * s + 12 + r], o[16 * s + 13 + r]))
        int st = 0, ph_par = 0, nu = 1 << 30;
        CK_DECL;
        for (int i = 0;; ++i) {
            const uint32_t base = sb + st * STAGE_BYTES;
            bar_sync(2 + (i & 1), 256);
            CK(0);
            const uint4* src = ph + (i & 1) * 672 + (tid - 128);
            const uint4 p0 = src[0], p1 = src[128], p2 = src[256], p3 = src[384], p4 = src[512];
            const float alpha = reinterpret_cast<const float*>(ph + (i & 1) * 672 + 640)[tid - 128];
            nu = *s_nu;
            if (i + 2 < nu) bar_arrive(4 + (i & 1), 256);
            if (__any_sync(0xffffffffu, alpha != 1.f)) {
#pragma unroll
                for (int j = 0; j < 64; ++j) { o0[j] *= alpha; o1[j] *= alpha; o2[j] *= alpha; }
            }
            mbar_wait(barF + 24 * st, ph_par); mbar_wait(barF + 24 * st + 8, ph_par); mbar_wait(barF + 24 * st + 16, ph_par);
            CK(1);
            const uint64_t dh = make_desc(base, 8192, 1024), dl = make_desc(base + HI_BYTES, 2048, 1024);
            wg_fence();
            wgmma_n128t(o0, p4.x, p4.y, p4.z, p4.w, dl + 0 * 256, 1);
            wgmma_n128t(o0, p0.x, p0.y, p0.z, p0.w, dh + 0 * 128 + 0 * 1024, 1);
            wgmma_n128t(o0, p1.x, p1.y, p1.z, p1.w, dh + 1 * 128 + 0 * 1024, 1);
            wgmma_n128t(o0, p2.x, p2.y, p2.z, p2.w, dh + 2 * 128 + 0 * 1024, 1);
            wgmma_n128t(o0, p3.x, p3.y, p3.z, p3.w, dh + 3 * 128 + 0 * 1024, 1);
            wg_commit();
            wgmma_n128t(o1, p4.x, p4.y, p4.z, p4.w, dl + 1 * 256, 1);
            wgmma_n128t(o1, p0.x, p0.y, p0.z, p0.w, dh + 0 * 128 + 1 * 1024, 1);
            wgmma_n128t(o1, p1.x, p1.y, p1.z, p1.w, dh + 1 * 128 + 1 * 1024, 1);
            wgmma_n128t(o1, p2.x, p2.y, p2.z, p2.w, dh + 2 * 128 + 1 * 1024, 1);
            wgmma_n128t(o1, p3.x, p3.y, p3.z, p3.w, dh + 3 * 128 + 1 * 1024, 1);
            wg_commit();
            wgmma_n128t(o2, p4.x, p4.y, p4.z, p4.w, dl + 2 * 256, 1);
            wgmma_n128t(o2, p0.x, p0.y, p0.z, p0.w, dh + 0 * 128 + 2 * 1024, 1);
            wgmma_n128t(o2, p1.x, p1.y, p1.z, p1.w, dh + 1 * 128 + 2 * 1024, 1);
            wgmma_n128t(o2, p2.x, p2.y, p2.z, p2.w, dh + 2 * 128 + 2 * 1024, 1);
            wgmma_n128t(o2, p3.x, p3.y, p3.z, p3.w, dh + 3 * 128 + 2 * 1024, 1);
            wg_commit();
            const bool more = tid == 128 && pend < NUNITS - 3 * ncta;
            wg_wait2();
            if (i == nu - 1) {
                reg_fence(o0);
#pragma unroll
                for (int s = 0; s < 4; ++s) { st_part(dst + s * 32, PART(o0, 0)); st_part(dst + (12 + s) * 32, PART(o0, 2)); }
            }
            bar_sync(6, 128);
            load_piece_if(more, base, &mp.hi, &mp.lo, pend + 3 * ncta, 0, barF + 24 * st, pol);
            wg_wait1();
            bar_sync(6, 128);
            load_piece_if(more, base, &mp.hi, &mp.lo, pend + 3 * ncta, 1, barF + 24 * st + 8, pol);
            if (i == nu - 1) break;
            wg_wait0();
            reg_fence(o0); reg_fence(o1); reg_fence(o2);
            CK(2);
            bar_sync(6, 128);
            if (tid == 128) {
                if (more) {
                    load_piece(base, &mp.hi, &mp.lo, pend + 3 * ncta, 2, barF + 24 * st + 16, pol);
                    pend = atomicAdd(&g_ctr[tag], 1);
                } else if (nu > i + 3) {
                    nu = i + 3;
                    *s_nu = nu;
                    asm volatile("mbarrier.arrive.shared::cta.b64 _, [%0];" :: "r"(barF + 24 * st) : "memory");
                }
                if (tail) {
                    if (i == 0) {
                        mbar_expect(barW + 8, 24576);
                        for (int k = 0; k < 4; ++k) tma2d(sb + OFF_WS + k * 6144, k < 2 ? &mp.lath : &mp.latl, sl * 16, (k & 1) * 192, barW + 8);
                    }
                    if (i == nu - 3) {
                        mbar_expect(barW + 16, STAGE_BYTES);
                        for (int k = 0; k < 2; ++k) {
                            tma2d(base + HI_BYTES + k * 6144, &mp.wkv, C + sl * 16, k * 192, barW + 16);
                            tma2d(base + k * 24576, &mp.w1, sl * 64, k * 192, barW + 16);
                        }
                    } else if (i == nu - 2) {
                        mbar_expect(barW + 24, STAGE_BYTES);
                        for (int k = 0; k < 2; ++k) tma2d(base + HI_BYTES + k * 6144, &mp.wo, sl * 16, k * 192, barW + 24);
                        for (int k = 0; k < 8; ++k) tma2d(base + k * 6144, &mp.w2, sl * 16, k * 192, barW + 24);
                    }
                }
            }
            if (++st == 3) { st = 0; ph_par ^= 1; }
            CK(3);
        }
        wg_wait1();
        reg_fence(o0); reg_fence(o1);
        STAMP(24); CK_OUT(4);
#pragma unroll
        for (int s = 0; s < 4; ++s) { st_part(dst + (4 + s) * 32, PART(o1, 0)); st_part(dst + (16 + s) * 32, PART(o1, 2)); }
        wg_wait0();
        reg_fence(o2);
        bar_sync(7, 256);
        const uint2 mlv = reinterpret_cast<const uint2*>(stat + 128)[w4 * 8 + g];
#pragma unroll
        for (int s = 0; s < 4; ++s) { st_part(dst + (8 + s) * 32, PART(o2, 0)); st_part(dst + (20 + s) * 32, PART(o2, 2)); }
        if (t == 0) st_ll(&g_x.ml[cta * 32 + w4 * 8 + g], mlv);
        STAMP(25);
    }
    if (!tail) return;

    const int nu = *s_nu;
    const uint32_t sA = sb + (nu % 3) * STAGE_BYTES, sB = sb + ((nu + 1) % 3) * STAGE_BYTES;
    float* red = reinterpret_cast<float*>(sp + OFF_PH);
    uint2 qres = make_uint2(0u, 0u);
    if (warp == 0) qres = make_uint2(__ldg(reinterpret_cast<const uint32_t*>(q) + xq), __ldg(reinterpret_cast<const uint32_t*>(q) + xq + 4));
    float c[4] = {0.f, 0.f, 0.f, 0.f}, c2[4] = {0.f, 0.f, 0.f, 0.f};
    {
        uint4 v[17]; uint2 ml[17];
        const bool extra = warp + 128 < ncta;
        const uint4* pv = &g_x.part[((warp * 4 + rg) * 24 + sl) * 32 + lane];
        const uint2* pm = &g_x.ml[warp * 32 + rg * 8 + g];
        v[16] = make_uint4(tag, 0u, 0u, 0u); ml[16] = make_uint2(tag, 0xff800000u);
        uint32_t seen = extra ? 0u : 1u << 16, done = seen;
        const uint32_t flip = tag ? 0u : 0x1ffffu;
        for (int it = 0; it < SPIN_LIMIT && seen != 0x1ffffu; ++it) {
            const uint32_t want = seen & ~done;
            uint32_t okm = 0, okv = 0;
#pragma unroll
            for (int i = 0; i < 17; ++i) {
                if (!(seen >> i & 1)) ld_ll(ml[i], pm + i * 256);
                if (want >> i & 1) ld_ll(v[i], pv + i * (8 * 4 * 24 * 32));
            }
#pragma unroll
            for (int i = 0; i < 17; ++i) { okm |= (ml[i].x & 1) << i; okv |= (v[i].x & 1) << i; }
            seen |= __reduce_and_sync(0xffffffffu, okm ^ flip);
            done |= want & __reduce_and_sync(0xffffffffu, okv ^ flip);
        }
        STAMP(21);
        uint32_t f2[17];
        float mw = 0.f, lw = 0.f;
        for (int it = 0; it < SPIN_LIMIT; ++it) {
#pragma unroll
            for (int i = 0; i < 17; ++i) if (!(done >> i & 1)) ld_ll(v[i], pv + i * (8 * 4 * 24 * 32));
            if (it == 0) {
                mw = __uint_as_float(ml[0].y);
#pragma unroll
                for (int i = 1; i < 17; ++i) mw = fmaxf(mw, __uint_as_float(ml[i].y));
#pragma unroll
                for (int i = 0; i < 17; ++i) {
                    const float f = ex2(__uint_as_float(ml[i].y) - mw);
                    f2[i] = pack2(f, f);
                    lw = fmaf(bf_lo(f2[i]), __uint_as_float(ml[i].x), lw);
                }
            }
            uint32_t bad = 0;
#pragma unroll
            for (int i = 0; i < 17; ++i) bad |= v[i].x ^ tag;
            if (!__any_sync(0xffffffffu, bad & 1)) break;
            done = extra ? 0u : 1u << 16;
        }
        STAMP(6);
        const uint32_t id = g == 2 * t ? 0x3F80u : (g == 2 * t + 1 ? 0x3F800000u : 0u);
        float e[3][4], e2[3][4];
#pragma unroll
        for (int i = 0; i < 3; ++i)
#pragma unroll
            for (int j = 0; j < 4; ++j) e[i][j] = e2[i][j] = 0.f;
#pragma unroll
        for (int i = 0; i < 17; ++i) {
            mma16816(e[i % 3], id, 0u, 0u, id, hmul_bf2(v[i].x, f2[i]), hmul_bf2(v[i].y, f2[i]));
            mma16816(e2[i % 3], id, 0u, 0u, id, hmul_bf2(v[i].z, f2[i]), hmul_bf2(v[i].w, f2[i]));
        }
#pragma unroll
        for (int j = 0; j < 4; ++j) { c[j] = e[0][j] + e[1][j] + e[2][j]; c2[j] = e2[0][j] + e2[1][j] + e2[2][j]; }
        red_put<40>(red, warp, lane, 0, c);
        red_put<40>(red, warp, lane, 16, c2);
        if (t == 0) { stat[g * 8 + warp] = mw; stat[64 + g * 8 + warp] = lw; }
        STAMP(23);
        bar_sync(1, 256);
        if (warp < 2) {
            float mv[8], lv[8];
            *reinterpret_cast<float4*>(mv) = *reinterpret_cast<const float4*>(stat + g * 8);
            *reinterpret_cast<float4*>(mv + 4) = *reinterpret_cast<const float4*>(stat + g * 8 + 4);
            *reinterpret_cast<float4*>(lv) = *reinterpret_cast<const float4*>(stat + 64 + g * 8);
            *reinterpret_cast<float4*>(lv + 4) = *reinterpret_cast<const float4*>(stat + 64 + g * 8 + 4);
            const float mm = fmaxf(fmaxf(fmaxf(mv[0], mv[1]), fmaxf(mv[2], mv[3])), fmaxf(fmaxf(mv[4], mv[5]), fmaxf(mv[6], mv[7])));
            float l = 0.f;
            float4 s = make_float4(0.f, 0.f, 0.f, 0.f);
#pragma unroll
            for (int w = 0; w < 8; ++w) {
                const float f = ex2(mv[w] - mm);
                const float* p = red + (w * 8 + g) * 40 + warp * 16 + 2 * t;
                const float2 x0 = *reinterpret_cast<const float2*>(p), x1 = *reinterpret_cast<const float2*>(p + 8);
                const float4 x = make_float4(x0.x, x0.y, x1.x, x1.y);
                l = fmaf(f, lv[w], l);
                s.x = fmaf(f, x.x, s.x); s.y = fmaf(f, x.y, s.y); s.z = fmaf(f, x.z, s.z); s.w = fmaf(f, x.w, s.w);
            }
            const float r = __frcp_rn(l);
            st_bf4(g_x.a, (rg * 48 + sl * 2 + warp) * 32 + lane, make_float4(s.x * r, s.y * r, s.z * r, s.w * r), tag);
            if (cta == 0 && tid == 0) asm volatile("st.relaxed.gpu.global.u32 [%0], %1;" :: "l"(&g_epoch), "r"(tag) : "memory");
        }
        STAMP(7);
    }
    uint2 v[6];
    uint32_t a[6][8];
    const int xn = (rg * 24 + w4 * 6) * 32 + lane;
    {
        mbar_wait(barW + 8, 0);
#pragma unroll
        for (int j = 0; j < 3; ++j) ld_w16(a[j], sb + OFF_WS, warp * 96 + j * 32, lane);
        poll<6, false>(v, reinterpret_cast<const uint2*>(g_x.a) + (rg * 48 + warp * 6) * 32 + lane, 32, tag);
        mma96(c, a[0], a[1], a[2], v);
        red_put<24>(red + 2560, warp, lane, 0, c);
        bar_sync(1, 256);
        if (warp == 0) st_bf4(g_x.m, x8, red_getn<24, 8>(red + 2560, lane, 0), tag);
        STAMP(8);
    }
    float4 h = make_float4(0.f, 0.f, 0.f, 0.f);
    mbar_wait(barW + 16, 0);
    mbar_wait(barW + 24, 0);
    STAMP(16);
    if (warp < 4) {
#pragma unroll
        for (int j = 0; j < 3; ++j) { ld_w16(a[j], sA + HI_BYTES, w4 * 96 + j * 32, lane); ld_w16(a[3 + j], sB + HI_BYTES, w4 * 96 + j * 32, lane); }
        STAMP(22);
        poll<6, false>(v, reinterpret_cast<const uint2*>(g_x.m) + xn, 32, tag);
        STAMP(17);
        mma96(c, a[0], a[1], a[2], v);
        red_put<24>(red, w4, lane, 0, c);
        bar_sync(9, 128);
        if (warp == 0) st_bf4(g_x.o, x8, red_getn<24, 4>(red, lane, 0), tag);
        STAMP(9);
        poll<6, false>(v, reinterpret_cast<const uint2*>(g_x.o) + xn, 32, tag);
        mma96(c, a[3], a[4], a[5], v);
        red_put<24>(red + 768, w4, lane, 0, c);
        bar_sync(9, 128);
        if (warp == 0) {
            h = red_getn<24, 4>(red + 768, lane, 0);
            h.x += bf_lo(qres.x); h.y += bf_hi(qres.x); h.z += bf_lo(qres.y); h.w += bf_hi(qres.y);
            st_bf4(g_x.h, x8, h, tag);
        }
        STAMP(10);
        bar_arrive(12, 256);
    }
    {
        const int wg = warp >> 2;
#pragma unroll
        for (int j = 0; j < 6; ++j) {
            const int k = w4 * 96 + (j >> 1) * 32 + (lane & 7) + ((lane >> 4) << 3), ch = wg * 4 + (j & 1) * 2 + ((lane >> 3) & 1);
            const uint32_t p = sA + k * 128 + ((ch ^ (lane & 7)) << 4);
            ldsm4t(*reinterpret_cast<uint32_t(*)[4]>(&a[j][0]), p);
            ldsm4t(*reinterpret_cast<uint32_t(*)[4]>(&a[j][4]), p + 2048);
        }
#pragma unroll
        for (int j = 0; j < 6; ++j) v[j] = make_uint2(0x3F803F80u, 0x3F803F80u);
        mma96(c, a[0], a[2], a[4], v); mma96(c2, a[1], a[3], a[5], v);
        float* cs = red + 4096 + wg * 128;
        if (t == 0) { cs[g * 4 + w4] = c[0]; cs[(g + 8) * 4 + w4] = c[2]; cs[(g + 16) * 4 + w4] = c2[0]; cs[(g + 24) * 4 + w4] = c2[2]; }
        bar_sync(10 + wg, 128);
        float cv[4];
#pragma unroll
        for (int j = 0; j < 4; ++j) {
            const float4 u = *reinterpret_cast<const float4*>(cs + ((w4 & 1) * 16 + 2 * t + (j & 1) + (j >> 1) * 8) * 4);
            cv[j] = (u.x + u.y) + (u.z + u.w);
        }
        if (wg) bar_sync(12, 256);
        poll<6, false>(v, reinterpret_cast<const uint2*>(g_x.h) + xn, 32, tag);
        STAMP(18);
        mma96(c, a[0], a[2], a[4], v); mma96(c2, a[1], a[3], a[5], v);
        float x[24], m = 0.f, q0 = 0.f, q1 = 0.f;
#pragma unroll
        for (int i = 0; i < 6; ++i) {
            x[4 * i] = bf_lo(v[i].x); x[4 * i + 1] = bf_hi(v[i].x); x[4 * i + 2] = bf_lo(v[i].y); x[4 * i + 3] = bf_hi(v[i].y);
            m += (x[4 * i] + x[4 * i + 1]) + (x[4 * i + 2] + x[4 * i + 3]);
        }
        m *= 1.f / 24;
#pragma unroll
        for (int i = 0; i < 24; i += 2) { q0 = fmaf(x[i] - m, x[i] - m, q0); q1 = fmaf(x[i + 1] - m, x[i + 1] - m, q1); }
        q0 += q1;
#pragma unroll
        for (int i = 1; i <= 2; ++i) {
            const float mo = __shfl_xor_sync(0xffffffffu, m, i), qo = __shfl_xor_sync(0xffffffffu, q0, i), d = m - mo;
            m = 0.5f * (m + mo);
            q0 = fmaf(d * d, 12.f * i, q0 + qo);
        }
        float2* st = reinterpret_cast<float2*>(stat) + wg * 32 + g * 4;
        if (t == 0) st[w4] = make_float2(m, q0);
        STAMP(19);
        float* rw = red + 1536 + wg * 1280;
        red_put<40>(rw, w4, lane, 0, c);
        red_put<40>(rw, w4, lane, 16, c2);
        bar_sync(10 + wg, 128);
        if (w4 < 2) {
            const float4 u0 = *reinterpret_cast<const float4*>(st), u1 = *reinterpret_cast<const float4*>(st + 2);
            const float4 s = red_getn<40, 4>(rw, lane, w4 * 16);
            const float mean = ((u0.x + u0.z) + (u1.x + u1.z)) * 0.25f;
            const float d0 = u0.x - mean, d1 = u0.z - mean, d2 = u1.x - mean, d3 = u1.z - mean;
            const float var = ((u0.y + u0.w) + (u1.y + u1.w)) * (1.f / C) + ((d0 * d0 + d1 * d1) + (d2 * d2 + d3 * d3)) * 0.25f;
            const float rs = rsqrtf(var + 1e-5f);
            st_bf4(g_x.g, (rg * 96 + sl * 4 + wg * 2 + w4) * 32 + lane,
                   make_float4(gelu_tanh(rs * fmaf(-mean, cv[0], s.x)), gelu_tanh(rs * fmaf(-mean, cv[1], s.y)),
                               gelu_tanh(rs * fmaf(-mean, cv[2], s.z)), gelu_tanh(rs * fmaf(-mean, cv[3], s.w))), tag);
        }
        STAMP(11);
    }
    {
#pragma unroll
        for (int j = 0; j < 6; ++j) ld_w16(a[j], sB, warp * 192 + j * 32, lane);
        uint2 gv[12];
        poll<12, false>(gv, reinterpret_cast<const uint2*>(g_x.g) + (rg * 96 + warp * 12) * 32 + lane, 32, tag);
        STAMP(20);
        mma96(c, a[0], a[1], a[2], gv); mma96(c2, a[3], a[4], a[5], gv + 6);
#pragma unroll
        for (int j = 0; j < 4; ++j) c[j] += c2[j];
        red_put<24>(red, warp, lane, 0, c);
        bar_sync(1, 256);
        if (warp == 0) {
            const float4 s = red_getn<24, 8>(red, lane, 0);
            reinterpret_cast<uint32_t*>(out)[xq] = pack2(h.x + s.x, h.y + s.y);
            reinterpret_cast<uint32_t*>(out)[xq + 4] = pack2(h.z + s.z, h.w + s.w);
        }
        STAMP(12);
    }
}

typedef CUresult (*EncodeFn)(CUtensorMap*, CUtensorMapDataType, cuuint32_t, void*, const cuuint64_t*, const cuuint64_t*,
                             const cuuint32_t*, const cuuint32_t*, CUtensorMapInterleave, CUtensorMapSwizzle,
                             CUtensorMapL2promotion, CUtensorMapFloatOOBfill);

void encode(EncodeFn fn, CUtensorMap* m, const void* p, int rank, const cuuint64_t* dim, const cuuint64_t* str,
            const cuuint32_t* box, CUtensorMapSwizzle sw, CUtensorMapL2promotion pr) {
    const cuuint32_t es[5] = {1, 1, 1, 1, 1};
    fn(m, CU_TENSOR_MAP_DATA_TYPE_BFLOAT16, rank, const_cast<void*>(p), dim, str, box, es, CU_TENSOR_MAP_INTERLEAVE_NONE, sw, pr,
       CU_TENSOR_MAP_FLOAT_OOB_FILL_NONE);
}
void encode2d(EncodeFn fn, CUtensorMap* m, const void* p, int w, int h, int bw) {
    const cuuint64_t dim[2] = {(cuuint64_t)w, (cuuint64_t)h}, str[1] = {(cuuint64_t)w * 2};
    const cuuint32_t box[2] = {(cuuint32_t)bw, 192};
    encode(fn, m, p, 2, dim, str, box, bw == 64 ? CU_TENSOR_MAP_SWIZZLE_128B : CU_TENSOR_MAP_SWIZZLE_32B, CU_TENSOR_MAP_L2_PROMOTION_L2_256B);
}

}

extern "C" void kernel_launch(void* const* d_in, const int* in_sizes, int n_in, void* d_out, int out_size) {
    typedef const __nv_bfloat16* BP;
    static EncodeFn fn = nullptr;
    if (!fn) {
        void* p = nullptr;
        cudaDriverEntryPointQueryResult qr;
        cudaGetDriverEntryPoint("cuTensorMapEncodeTiled", &p, cudaEnableDefault, &qr);
        fn = (EncodeFn)p;
        cudaFuncSetAttribute(detr_kernel, cudaFuncAttributeMaxDynamicSharedMemorySize, SMEM_BYTES);
    }
    Maps mp;
    {
        const cuuint64_t dim[5] = {64, 192, 2, 384, 6}, str[4] = {1536, 768, 384 * 768, 128};
        const cuuint32_t box[5] = {64, 16, 2, 2, 2};
        encode(fn, &mp.hi, d_in[1], 5, dim, str, box, CU_TENSOR_MAP_SWIZZLE_128B, FEAT_PROMO);
    }
    {
        const cuuint64_t dim[3] = {64, 192 * 192, 6}, str[2] = {768, 128};
        const cuuint32_t box[3] = {64, 16, 2};
        encode(fn, &mp.lo, d_in[2], 3, dim, str, box, CU_TENSOR_MAP_SWIZZLE_128B, FEAT_PROMO);
    }
    encode2d(fn, &mp.lath, d_in[3], C, C, 16);
    encode2d(fn, &mp.latl, d_in[4], C, C, 16);
    encode2d(fn, &mp.wq, d_in[5], C, C, 16);
    encode2d(fn, &mp.wkv, d_in[6], 2 * C, C, 16);
    encode2d(fn, &mp.wo, d_in[7], C, C, 16);
    encode2d(fn, &mp.w1, d_in[8], 4 * C, C, 64);
    encode2d(fn, &mp.w2, d_in[9], C, 4 * C, 16);
    detr_kernel<<<MAXCTA, NTHREADS, SMEM_BYTES, cudaStreamPerThread>>>(mp, (BP)d_in[0], (BP)d_in[1], (BP)d_in[2], (BP)d_in[3], (BP)d_in[4],
                                                                       (BP)d_in[6], (__nv_bfloat16*)d_out, MAXCTA);
}
```
